```python
import torch

def _softmax(x, axis=-1):
    return torch.softmax(x, dim=axis)
def _gelu(x):
    return torch.nn.functional.gelu(x, approximate="tanh")
def _silu(x):
    return torch.nn.functional.silu(x)
def _sigmoid(x):
    return torch.sigmoid(x)
def _layernorm(x, axis=-1, eps=1e-5):
    m = x.mean(dim=axis, keepdim=True)
    v = x.var(dim=axis, keepdim=True, unbiased=False)
    return (x - m) / torch.sqrt(v + eps)
def _scatter_add(tgt, idx, src, axis=0):
    return tgt.clone().index_add_(axis, idx, src)
def _segment_sum(src, seg, n):
    out = torch.zeros((n,) + src.shape[1:], dtype=src.dtype)
    return out.index_add_(0, seg, src)
def _pad(x, pw):
    flat = tuple(v for pair in reversed(pw) for v in pair)
    return torch.nn.functional.pad(x, flat)

kernel_name = 'sequential_preLN__softmax_full_mha__swiglu_ffn__prompt'

def setup_inputs():

    _w = (lambda a: (lambda t: t.to(torch.bfloat16) if t.is_floating_point() else t)(torch.as_tensor(a)))
    def _A_setup():
        B, S, D = 1, 2048, 640
        return {
            "x": _w((lambda *s: torch.randn(*s, dtype=torch.bfloat16) * 0.05)(B, S, D)),
            "wqkv": _w((lambda *s: torch.randn(*s, dtype=torch.bfloat16) * 0.05)(D, 3 * D)),
            "wo": _w((lambda *s: torch.randn(*s, dtype=torch.bfloat16) * 0.05)(D, D)),
        }
    _A_in = _A_setup()

    def _B_setup():
        B, S, D, F = 1, 2048, 640, 1536
        return {
            "x": _w((lambda *s: torch.randn(*s, dtype=torch.bfloat16) * 0.05)(B, S, D)),
            "w_gate": _w((lambda *s: torch.randn(*s, dtype=torch.bfloat16) * 0.05)(D, F)),
            "w_up": _w((lambda *s: torch.randn(*s, dtype=torch.bfloat16) * 0.05)(D, F)),
            "w_down": _w((lambda *s: torch.randn(*s, dtype=torch.bfloat16) * 0.05)(F, D)),
        }
    _B_in = _B_setup()

    return {
        "A_x": _A_in["x"],
        "A_wqkv": _A_in["wqkv"],
        "A_wo": _A_in["wo"],
        "B_x": _B_in["x"],
        "B_w_gate": _B_in["w_gate"],
        "B_w_up": _B_in["w_up"],
        "B_w_down": _B_in["w_down"],
    }

def reference(A_x, A_wqkv, A_wo, B_x, B_w_gate, B_w_up, B_w_down):
    def _A_ref(x, wqkv, wo):
        B, S, D = x.shape
        H = 32; Dh = D // H
        qkv = (lambda x, *d: x.permute(*d))((x @ wqkv).reshape(B, S, 3, H, Dh), 2, 0, 3, 1, 4)
        q, k, v = qkv[0], qkv[1], qkv[2]
        scale = Dh ** -0.5
        scores = torch.einsum("bhqd,bhkd->bhqk", q, k) * scale
        p = _softmax(scores, axis=-1)
        o = torch.einsum("bhqk,bhkd->bhqd", p, v)
        return (lambda x, *d: x.permute(*d))(o, 0, 2, 1, 3).reshape(B, S, D) @ wo

    def _B_ref(x, w_gate, w_up, w_down):
        g = _silu(x @ w_gate)
        u = x @ w_up
        return (g * u) @ w_down

    x = A_x
    h = x + _A_ref(_layernorm(x, axis=-1), A_wqkv, A_wo)
    h2 = h + _B_ref(_layernorm(h, axis=-1), B_w_gate, B_w_up, B_w_down)
    return h2
```

```cpp
#include <cuda_runtime.h>
#include <cuda_bf16.h>
#include <cuda.h>
#include <stdint.h>

typedef __nv_bfloat16 bf16;
constexpr int SEQ = 2048, DM = 640, NH = 32, DH = 20, FF = 1536;

__device__ __align__(1024) bf16 g_ln[SEQ * DM];
__device__ __align__(1024) bf16 g_q[NH * SEQ * 32];
__device__ __align__(1024) bf16 g_k[NH * SEQ * 32];
__device__ __align__(1024) bf16 g_v[NH * SEQ * 24];
__device__ __align__(1024) bf16 g_attn[SEQ * DM];
__device__ __align__(1024) bf16 g_h[SEQ * DM];
__device__ __align__(1024) bf16 g_act[SEQ * FF];

__device__ __forceinline__ uint32_t smem_u32(const void* p) { return (uint32_t)__cvta_generic_to_shared(p); }
__device__ __forceinline__ void mbar_init(uint32_t bar, uint32_t cnt) {
  asm volatile("mbarrier.init.shared::cta.b64 [%0], %1;" :: "r"(bar), "r"(cnt) : "memory");
}
__device__ __forceinline__ void mbar_expect_tx(uint32_t bar, uint32_t bytes) {
  asm volatile("mbarrier.arrive.expect_tx.shared::cta.b64 _, [%0], %1;" :: "r"(bar), "r"(bytes) : "memory");
}
__device__ __forceinline__ void mbar_arrive(uint32_t bar) {
  asm volatile("mbarrier.arrive.shared::cta.b64 _, [%0];" :: "r"(bar) : "memory");
}
__device__ __forceinline__ void mbar_wait(uint32_t bar, uint32_t parity) {
  uint32_t ok;
  #pragma unroll 1
  for (uint32_t it = 0; it < 0x10000000u; ++it) {
    asm volatile("{\n.reg .pred p;\nmbarrier.try_wait.parity.shared::cta.b64 p, [%1], %2;\nselp.u32 %0, 1, 0, p;\n}\n"
                 : "=r"(ok) : "r"(bar), "r"(parity) : "memory");
    if (ok) break;
  }
}
__device__ __forceinline__ void tma_2d(uint32_t dst, const CUtensorMap* tm, int c0, int c1, uint32_t bar) {
  asm volatile("cp.async.bulk.tensor.2d.shared::cluster.global.mbarrier::complete_tx::bytes [%0], [%1, {%3, %4}], [%2];"
               :: "r"(dst), "l"(tm), "r"(bar), "r"(c0), "r"(c1) : "memory");
}
__device__ __forceinline__ void bulk_1d(uint32_t dst, const void* src, uint32_t bytes, uint32_t bar) {
  asm volatile("cp.async.bulk.shared::cluster.global.mbarrier::complete_tx::bytes [%0], [%1], %2, [%3];"
               :: "r"(dst), "l"(src), "r"(bytes), "r"(bar) : "memory");
}
__device__ __forceinline__ void wg_fence() { asm volatile("wgmma.fence.sync.aligned;" ::: "memory"); }
__device__ __forceinline__ void wg_commit() { asm volatile("wgmma.commit_group.sync.aligned;" ::: "memory"); }
template <int N> __device__ __forceinline__ void wg_wait() { asm volatile("wgmma.wait_group.sync.aligned %0;" :: "n"(N) : "memory"); }
__device__ __forceinline__ uint64_t mk_desc(uint32_t addr, uint32_t lbo, uint32_t sbo, uint32_t mode) {
  return (uint64_t)((addr & 0x3FFFF) >> 4) | ((uint64_t)(lbo >> 4) << 16) | ((uint64_t)(sbo >> 4) << 32) | ((uint64_t)mode << 62);
}
__device__ __forceinline__ float bf16r(float x) { return __bfloat162float(__float2bfloat16_rn(x)); }
__device__ __forceinline__ uint32_t pack2(float lo, float hi) {
  __nv_bfloat162 v = __floats2bfloat162_rn(lo, hi);
  return *reinterpret_cast<uint32_t*>(&v);
}
__device__ __forceinline__ float ex2(float x) { float y; asm("ex2.approx.ftz.f32 %0, %1;" : "=f"(y) : "f"(x)); return y; }

__device__ __forceinline__ void wgmma_ss_n240_tb1(float (&d)[120], uint64_t da, uint64_t db, int sd) {
  asm volatile("{\n.reg .pred p;\nsetp.ne.b32 p, %122, 0;\n"
    "wgmma.mma_async.sync.aligned.m64n240k16.f32.bf16.bf16 {%0, %1, %2, %3, %4, %5, %6, %7, %8, %9, %10, %11, %12, %13, %14, %15, %16, %17, %18, %19, %20, %21, %22, %23, %24, %25, %26, %27, %28, %29, %30, %31, %32, %33, %34, %35, %36, %37, %38, %39, %40, %41, %42, %43, %44, %45, %46, %47, %48, %49, %50, %51, %52, %53, %54, %55, %56, %57, %58, %59, %60, %61, %62, %63, %64, %65, %66, %67, %68, %69, %70, %71, %72, %73, %74, %75, %76, %77, %78, %79, %80, %81, %82, %83, %84, %85, %86, %87, %88, %89, %90, %91, %92, %93, %94, %95, %96, %97, %98, %99, %100, %101, %102, %103, %104, %105, %106, %107, %108, %109, %110, %111, %112, %113, %114, %115, %116, %117, %118, %119}, %120, %121, p, 1, 1, 0, 1;\n}\n"
    : "+f"(d[0]), "+f"(d[1]), "+f"(d[2]), "+f"(d[3]), "+f"(d[4]), "+f"(d[5]), "+f"(d[6]), "+f"(d[7]), "+f"(d[8]), "+f"(d[9]), "+f"(d[10]), "+f"(d[11]), "+f"(d[12]), "+f"(d[13]), "+f"(d[14]), "+f"(d[15]), "+f"(d[16]), "+f"(d[17]), "+f"(d[18]), "+f"(d[19]), "+f"(d[20]), "+f"(d[21]), "+f"(d[22]), "+f"(d[23]), "+f"(d[24]), "+f"(d[25]), "+f"(d[26]), "+f"(d[27]), "+f"(d[28]), "+f"(d[29]), "+f"(d[30]), "+f"(d[31]), "+f"(d[32]), "+f"(d[33]), "+f"(d[34]), "+f"(d[35]), "+f"(d[36]), "+f"(d[37]), "+f"(d[38]), "+f"(d[39]), "+f"(d[40]), "+f"(d[41]), "+f"(d[42]), "+f"(d[43]), "+f"(d[44]), "+f"(d[45]), "+f"(d[46]), "+f"(d[47]), "+f"(d[48]), "+f"(d[49]), "+f"(d[50]), "+f"(d[51]), "+f"(d[52]), "+f"(d[53]), "+f"(d[54]), "+f"(d[55]), "+f"(d[56]), "+f"(d[57]), "+f"(d[58]), "+f"(d[59]), "+f"(d[60]), "+f"(d[61]), "+f"(d[62]), "+f"(d[63]), "+f"(d[64]), "+f"(d[65]), "+f"(d[66]), "+f"(d[67]), "+f"(d[68]), "+f"(d[69]), "+f"(d[70]), "+f"(d[71]), "+f"(d[72]), "+f"(d[73]), "+f"(d[74]), "+f"(d[75]), "+f"(d[76]), "+f"(d[77]), "+f"(d[78]), "+f"(d[79]), "+f"(d[80]), "+f"(d[81]), "+f"(d[82]), "+f"(d[83]), "+f"(d[84]), "+f"(d[85]), "+f"(d[86]), "+f"(d[87]), "+f"(d[88]), "+f"(d[89]), "+f"(d[90]), "+f"(d[91]), "+f"(d[92]), "+f"(d[93]), "+f"(d[94]), "+f"(d[95]), "+f"(d[96]), "+f"(d[97]), "+f"(d[98]), "+f"(d[99]), "+f"(d[100]), "+f"(d[101]), "+f"(d[102]), "+f"(d[103]), "+f"(d[104]), "+f"(d[105]), "+f"(d[106]), "+f"(d[107]), "+f"(d[108]), "+f"(d[109]), "+f"(d[110]), "+f"(d[111]), "+f"(d[112]), "+f"(d[113]), "+f"(d[114]), "+f"(d[115]), "+f"(d[116]), "+f"(d[117]), "+f"(d[118]), "+f"(d[119])
    : "l"(da), "l"(db), "r"(sd));
}
__device__ __forceinline__ void wgmma_ss_n80_tb1(float (&d)[40], uint64_t da, uint64_t db, int sd) {
  asm volatile("{\n.reg .pred p;\nsetp.ne.b32 p, %42, 0;\n"
    "wgmma.mma_async.sync.aligned.m64n80k16.f32.bf16.bf16 {%0, %1, %2, %3, %4, %5, %6, %7, %8, %9, %10, %11, %12, %13, %14, %15, %16, %17, %18, %19, %20, %21, %22, %23, %24, %25, %26, %27, %28, %29, %30, %31, %32, %33, %34, %35, %36, %37, %38, %39}, %40, %41, p, 1, 1, 0, 1;\n}\n"
    : "+f"(d[0]), "+f"(d[1]), "+f"(d[2]), "+f"(d[3]), "+f"(d[4]), "+f"(d[5]), "+f"(d[6]), "+f"(d[7]), "+f"(d[8]), "+f"(d[9]), "+f"(d[10]), "+f"(d[11]), "+f"(d[12]), "+f"(d[13]), "+f"(d[14]), "+f"(d[15]), "+f"(d[16]), "+f"(d[17]), "+f"(d[18]), "+f"(d[19]), "+f"(d[20]), "+f"(d[21]), "+f"(d[22]), "+f"(d[23]), "+f"(d[24]), "+f"(d[25]), "+f"(d[26]), "+f"(d[27]), "+f"(d[28]), "+f"(d[29]), "+f"(d[30]), "+f"(d[31]), "+f"(d[32]), "+f"(d[33]), "+f"(d[34]), "+f"(d[35]), "+f"(d[36]), "+f"(d[37]), "+f"(d[38]), "+f"(d[39])
    : "l"(da), "l"(db), "r"(sd));
}
__device__ __forceinline__ void wgmma_ss_n192_tb1(float (&d)[96], uint64_t da, uint64_t db, int sd) {
  asm volatile("{\n.reg .pred p;\nsetp.ne.b32 p, %98, 0;\n"
    "wgmma.mma_async.sync.aligned.m64n192k16.f32.bf16.bf16 {%0, %1, %2, %3, %4, %5, %6, %7, %8, %9, %10, %11, %12, %13, %14, %15, %16, %17, %18, %19, %20, %21, %22, %23, %24, %25, %26, %27, %28, %29, %30, %31, %32, %33, %34, %35, %36, %37, %38, %39, %40, %41, %42, %43, %44, %45, %46, %47, %48, %49, %50, %51, %52, %53, %54, %55, %56, %57, %58, %59, %60, %61, %62, %63, %64, %65, %66, %67, %68, %69, %70, %71, %72, %73, %74, %75, %76, %77, %78, %79, %80, %81, %82, %83, %84, %85, %86, %87, %88, %89, %90, %91, %92, %93, %94, %95}, %96, %97, p, 1, 1, 0, 1;\n}\n"
    : "+f"(d[0]), "+f"(d[1]), "+f"(d[2]), "+f"(d[3]), "+f"(d[4]), "+f"(d[5]), "+f"(d[6]), "+f"(d[7]), "+f"(d[8]), "+f"(d[9]), "+f"(d[10]), "+f"(d[11]), "+f"(d[12]), "+f"(d[13]), "+f"(d[14]), "+f"(d[15]), "+f"(d[16]), "+f"(d[17]), "+f"(d[18]), "+f"(d[19]), "+f"(d[20]), "+f"(d[21]), "+f"(d[22]), "+f"(d[23]), "+f"(d[24]), "+f"(d[25]), "+f"(d[26]), "+f"(d[27]), "+f"(d[28]), "+f"(d[29]), "+f"(d[30]), "+f"(d[31]), "+f"(d[32]), "+f"(d[33]), "+f"(d[34]), "+f"(d[35]), "+f"(d[36]), "+f"(d[37]), "+f"(d[38]), "+f"(d[39]), "+f"(d[40]), "+f"(d[41]), "+f"(d[42]), "+f"(d[43]), "+f"(d[44]), "+f"(d[45]), "+f"(d[46]), "+f"(d[47]), "+f"(d[48]), "+f"(d[49]), "+f"(d[50]), "+f"(d[51]), "+f"(d[52]), "+f"(d[53]), "+f"(d[54]), "+f"(d[55]), "+f"(d[56]), "+f"(d[57]), "+f"(d[58]), "+f"(d[59]), "+f"(d[60]), "+f"(d[61]), "+f"(d[62]), "+f"(d[63]), "+f"(d[64]), "+f"(d[65]), "+f"(d[66]), "+f"(d[67]), "+f"(d[68]), "+f"(d[69]), "+f"(d[70]), "+f"(d[71]), "+f"(d[72]), "+f"(d[73]), "+f"(d[74]), "+f"(d[75]), "+f"(d[76]), "+f"(d[77]), "+f"(d[78]), "+f"(d[79]), "+f"(d[80]), "+f"(d[81]), "+f"(d[82]), "+f"(d[83]), "+f"(d[84]), "+f"(d[85]), "+f"(d[86]), "+f"(d[87]), "+f"(d[88]), "+f"(d[89]), "+f"(d[90]), "+f"(d[91]), "+f"(d[92]), "+f"(d[93]), "+f"(d[94]), "+f"(d[95])
    : "l"(da), "l"(db), "r"(sd));
}
__device__ __forceinline__ void wgmma_ss_n128_tb0(float (&d)[64], uint64_t da, uint64_t db, int sd) {
  asm volatile("{\n.reg .pred p;\nsetp.ne.b32 p, %66, 0;\n"
    "wgmma.mma_async.sync.aligned.m64n128k16.f32.bf16.bf16 {%0, %1, %2, %3, %4, %5, %6, %7, %8, %9, %10, %11, %12, %13, %14, %15, %16, %17, %18, %19, %20, %21, %22, %23, %24, %25, %26, %27, %28, %29, %30, %31, %32, %33, %34, %35, %36, %37, %38, %39, %40, %41, %42, %43, %44, %45, %46, %47, %48, %49, %50, %51, %52, %53, %54, %55, %56, %57, %58, %59, %60, %61, %62, %63}, %64, %65, p, 1, 1, 0, 0;\n}\n"
    : "+f"(d[0]), "+f"(d[1]), "+f"(d[2]), "+f"(d[3]), "+f"(d[4]), "+f"(d[5]), "+f"(d[6]), "+f"(d[7]), "+f"(d[8]), "+f"(d[9]), "+f"(d[10]), "+f"(d[11]), "+f"(d[12]), "+f"(d[13]), "+f"(d[14]), "+f"(d[15]), "+f"(d[16]), "+f"(d[17]), "+f"(d[18]), "+f"(d[19]), "+f"(d[20]), "+f"(d[21]), "+f"(d[22]), "+f"(d[23]), "+f"(d[24]), "+f"(d[25]), "+f"(d[26]), "+f"(d[27]), "+f"(d[28]), "+f"(d[29]), "+f"(d[30]), "+f"(d[31]), "+f"(d[32]), "+f"(d[33]), "+f"(d[34]), "+f"(d[35]), "+f"(d[36]), "+f"(d[37]), "+f"(d[38]), "+f"(d[39]), "+f"(d[40]), "+f"(d[41]), "+f"(d[42]), "+f"(d[43]), "+f"(d[44]), "+f"(d[45]), "+f"(d[46]), "+f"(d[47]), "+f"(d[48]), "+f"(d[49]), "+f"(d[50]), "+f"(d[51]), "+f"(d[52]), "+f"(d[53]), "+f"(d[54]), "+f"(d[55]), "+f"(d[56]), "+f"(d[57]), "+f"(d[58]), "+f"(d[59]), "+f"(d[60]), "+f"(d[61]), "+f"(d[62]), "+f"(d[63])
    : "l"(da), "l"(db), "r"(sd));
}
__device__ __forceinline__ void wgmma_rs_n24_tb1(float (&d)[12], uint32_t a0, uint32_t a1, uint32_t a2, uint32_t a3, uint64_t db, int sd) {
  asm volatile("{\n.reg .pred p;\nsetp.ne.b32 p, %17, 0;\n"
    "wgmma.mma_async.sync.aligned.m64n24k16.f32.bf16.bf16 {%0, %1, %2, %3, %4, %5, %6, %7, %8, %9, %10, %11}, {%12, %13, %14, %15}, %16, p, 1, 1, 1;\n}\n"
    : "+f"(d[0]), "+f"(d[1]), "+f"(d[2]), "+f"(d[3]), "+f"(d[4]), "+f"(d[5]), "+f"(d[6]), "+f"(d[7]), "+f"(d[8]), "+f"(d[9]), "+f"(d[10]), "+f"(d[11])
    : "r"(a0), "r"(a1), "r"(a2), "r"(a3), "l"(db), "r"(sd));
}


__global__ void __launch_bounds__(256) ln_kernel(const bf16* __restrict__ x, bf16* __restrict__ y) {
  int row = blockIdx.x * 8 + (threadIdx.x >> 5), lane = threadIdx.x & 31;
  const uint4* src = reinterpret_cast<const uint4*>(x + (size_t)row * DM);
  float v[24]; float s = 0.f;
  #pragma unroll
  for (int i = 0; i < 3; ++i) {
    int c = lane + 32 * i;
    uint4 u = make_uint4(0, 0, 0, 0);
    if (c < 80) u = src[c];
    const __nv_bfloat162* p = reinterpret_cast<const __nv_bfloat162*>(&u);
    #pragma unroll
    for (int j = 0; j < 4; ++j) { float2 f = __bfloat1622float2(p[j]); v[i * 8 + 2 * j] = f.x; v[i * 8 + 2 * j + 1] = f.y; s += f.x + f.y; }
  }
  #pragma unroll
  for (int o = 16; o; o >>= 1) s += __shfl_xor_sync(~0u, s, o);
  float mean = s * (1.f / DM), q = 0.f;
  #pragma unroll
  for (int i = 0; i < 3; ++i) if (lane + 32 * i < 80) {
    #pragma unroll
    for (int j = 0; j < 8; ++j) { float d = v[i * 8 + j] - mean; q += d * d; }
  }
  #pragma unroll
  for (int o = 16; o; o >>= 1) q += __shfl_xor_sync(~0u, q, o);
  float mb = bf16r(mean), vb = bf16r(q * (1.f / DM));
  float den = bf16r(sqrtf(bf16r(vb + 1e-5f)));
  uint4* dst = reinterpret_cast<uint4*>(y + (size_t)row * DM);
  #pragma unroll
  for (int i = 0; i < 3; ++i) {
    int c = lane + 32 * i;
    if (c < 80) {
      uint4 u; uint32_t* w = reinterpret_cast<uint32_t*>(&u);
      #pragma unroll
      for (int j = 0; j < 4; ++j) w[j] = pack2(bf16r(v[i * 8 + 2 * j] - mb) / den, bf16r(v[i * 8 + 2 * j + 1] - mb) / den);
      dst[c] = u;
    }
  }
}

template <int MODE> struct GCfg;
template <> struct GCfg<0> { static constexpr int BN = 240, NBOX = 4, ST = 4, KT = 10; };
template <> struct GCfg<1> { static constexpr int BN = 80, NBOX = 2, ST = 6, KT = 10; };
template <> struct GCfg<2> { static constexpr int BN = 192, NBOX = 6, ST = 3, KT = 10; };
template <> struct GCfg<3> { static constexpr int BN = 80, NBOX = 2, ST = 6, KT = 24; };

template <int MODE>
__global__ void __launch_bounds__(384, 1) gemm_kernel(const __grid_constant__ CUtensorMap tmA, const __grid_constant__ CUtensorMap tmB,
                                                      const __grid_constant__ CUtensorMap tmB2, const bf16* __restrict__ resid, bf16* __restrict__ out) {
  using C = GCfg<MODE>;
  constexpr int STAGE = 16384 + C::NBOX * 8192;
  extern __shared__ __align__(1024) uint8_t smem_raw[];
  uint32_t sbase = (smem_u32(smem_raw) + 1023) & ~1023u;
  uint32_t bars = sbase + C::ST * STAGE;
  const int m0 = blockIdx.y * 128, n0 = blockIdx.x * C::BN;
  const int wg = threadIdx.x >> 7;
  if (threadIdx.x == 0) {
    for (int s = 0; s < C::ST; ++s) { mbar_init(bars + 8 * s, 1); mbar_init(bars + 8 * (C::ST + s), 2); }
    asm volatile("fence.mbarrier_init.release.cluster;" ::: "memory");
  }
  __syncthreads();
  if (wg == 0) {
    asm volatile("setmaxnreg.dec.sync.aligned.u32 40;");
    if (threadIdx.x == 0) {
      for (int kt = 0; kt < C::KT; ++kt) {
        int s = kt % C::ST; uint32_t ph = (kt / C::ST) & 1;
        mbar_wait(bars + 8 * (C::ST + s), ph ^ 1);
        uint32_t fb = bars + 8 * s, st = sbase + s * STAGE;
        mbar_expect_tx(fb, STAGE);
        tma_2d(st, &tmA, kt * 64, m0, fb);
        if (MODE == 2) {
          for (int b = 0; b < 3; ++b) tma_2d(st + 16384 + b * 8192, &tmB, n0 + b * 64, kt * 64, fb);
          for (int b = 0; b < 3; ++b) tma_2d(st + 16384 + (3 + b) * 8192, &tmB2, n0 + b * 64, kt * 64, fb);
        } else {
          for (int b = 0; b < C::NBOX; ++b) tma_2d(st + 16384 + b * 8192, &tmB, n0 + b * 64, kt * 64, fb);
        }
      }
    }
  } else {
    asm volatile("setmaxnreg.inc.sync.aligned.u32 232;");
    const int w = wg - 1;
    float acc[C::BN / 2];
    float acc2[MODE == 2 ? 96 : 2];
    for (int kt = 0; kt < C::KT; ++kt) {
      int s = kt % C::ST; uint32_t ph = (kt / C::ST) & 1;
      mbar_wait(bars + 8 * s, ph);
      uint32_t st = sbase + s * STAGE;
      uint64_t da = mk_desc(st + w * 8192, 16, 1024, 1);
      uint64_t db = mk_desc(st + 16384, 8192, 1024, 1);
      wg_fence();
      #pragma unroll
      for (int k = 0; k < 4; ++k) {
        int sd = (kt | k) != 0;
        if constexpr (MODE == 0) wgmma_ss_n240_tb1(acc, da + 2 * k, db + 128 * k, sd);
        else if constexpr (MODE == 2) {
          wgmma_ss_n192_tb1(acc, da + 2 * k, db + 128 * k, sd);
          wgmma_ss_n192_tb1(acc2, da + 2 * k, db + 128 * k + 3 * 512, sd);
        } else wgmma_ss_n80_tb1(acc, da + 2 * k, db + 128 * k, sd);
      }
      wg_commit();
      if (kt > 0) { wg_wait<1>(); if ((threadIdx.x & 127) == 0) mbar_arrive(bars + 8 * (C::ST + (kt - 1) % C::ST)); }
    }
    wg_wait<0>();
    const int t = threadIdx.x & 127, lane = t & 31;
    const int r0 = m0 + w * 64 + (t >> 5) * 16 + (lane >> 2), cq = 2 * (lane & 3);
    if constexpr (MODE == 0) {
      #pragma unroll
      for (int j = 0; j < 30; ++j) {
        int c = n0 + 8 * j + cq; int which = c / DM, cc = c - which * DM, hd = cc / DH, d = cc - hd * DH;
        #pragma unroll
        for (int hh = 0; hh < 2; ++hh) {
          int r = r0 + 8 * hh; uint32_t v = pack2(acc[4 * j + 2 * hh], acc[4 * j + 2 * hh + 1]);
          int inner = (d >> 3) * 64 + (r & 7) * 8 + (d & 7);
          if (which == 2) *reinterpret_cast<uint32_t*>(g_v + (size_t)hd * SEQ * 24 + (r >> 3) * 192 + inner) = v;
          else *reinterpret_cast<uint32_t*>((which ? g_k : g_q) + (size_t)hd * SEQ * 32 + (r >> 3) * 256 + inner) = v;
        }
      }
      for (int i = t; i < 64 * 12; i += 128) {
        int r = m0 + w * 64 + (i & 63); int c = n0 + (i >> 6) * DH; int which = c / DM, hd = (c - which * DM) / DH;
        if (which == 2) *reinterpret_cast<uint2*>(g_v + (size_t)hd * SEQ * 24 + (r >> 3) * 192 + 128 + (r & 7) * 8 + 4) = make_uint2(0x00003F80u, 0u);
        else {
          bf16* p = (which ? g_k : g_q) + (size_t)hd * SEQ * 32 + (r >> 3) * 256 + (r & 7) * 8;
          *reinterpret_cast<uint2*>(p + 128 + 4) = make_uint2(0u, 0u);
          *reinterpret_cast<uint4*>(p + 192) = make_uint4(0u, 0u, 0u, 0u);
        }
      }
    } else if constexpr (MODE == 2) {
      #pragma unroll
      for (int j = 0; j < 24; ++j) {
        #pragma unroll
        for (int hh = 0; hh < 2; ++hh) {
          float o[2];
          #pragma unroll
          for (int e = 0; e < 2; ++e) {
            float g = bf16r(acc[4 * j + 2 * hh + e]), u = bf16r(acc2[4 * j + 2 * hh + e]);
            o[e] = bf16r(g / (1.f + __expf(-g))) * u;
          }
          *reinterpret_cast<uint32_t*>(g_act + (size_t)(r0 + 8 * hh) * FF + n0 + 8 * j + cq) = pack2(o[0], o[1]);
        }
      }
    } else {
      #pragma unroll
      for (int j = 0; j < 10; ++j) {
        #pragma unroll
        for (int hh = 0; hh < 2; ++hh) {
          size_t off = (size_t)(r0 + 8 * hh) * DM + n0 + 8 * j + cq;
          float2 rv = __bfloat1622float2(*reinterpret_cast<const __nv_bfloat162*>(resid + off));
          *reinterpret_cast<uint32_t*>(out + off) = pack2(rv.x + bf16r(acc[4 * j + 2 * hh]), rv.y + bf16r(acc[4 * j + 2 * hh + 1]));
        }
      }
    }
  }
}

constexpr int AT_ST = 4, AT_KB = 8192, AT_VB = 6144, AT_STAGE = AT_KB + AT_VB;
__global__ void __launch_bounds__(512, 1) attn_kernel() {
  extern __shared__ __align__(1024) uint8_t smem_raw[];
  uint32_t sbase = (smem_u32(smem_raw) + 1023) & ~1023u;
  uint32_t sq = sbase, skv = sbase + 16384, bars = skv + AT_ST * AT_STAGE;
  const int hd = blockIdx.y, q0 = blockIdx.x * 256, wg = threadIdx.x >> 7, t = threadIdx.x & 127, lane = t & 31;
  const bf16* kg = g_k + (size_t)hd * SEQ * 32;
  const bf16* vg = g_v + (size_t)hd * SEQ * 24;
  if (threadIdx.x == 0) {
    for (int s = 0; s < AT_ST; ++s) { mbar_init(bars + 8 * s, 1); mbar_init(bars + 8 * (AT_ST + s), 4); }
    mbar_init(bars + 8 * 2 * AT_ST, 1);
    asm volatile("fence.mbarrier_init.release.cluster;" ::: "memory");
    mbar_expect_tx(bars + 16 * AT_ST, 16384);
    bulk_1d(sq, g_q + (size_t)hd * SEQ * 32 + (size_t)q0 * 32, 16384, bars + 16 * AT_ST);
    for (int s = 0; s < AT_ST; ++s) {
      mbar_expect_tx(bars + 8 * s, AT_STAGE);
      bulk_1d(skv + s * AT_STAGE, kg + (size_t)s * 128 * 32, AT_KB, bars + 8 * s);
      bulk_1d(skv + s * AT_STAGE + AT_KB, vg + (size_t)s * 128 * 24, AT_VB, bars + 8 * s);
    }
  }
  __syncthreads();
  const float cs = 0.22360679774997896f * 1.4426950408889634f;
  float o[12]; float m0 = -INFINITY, m1 = -INFINITY;
  #pragma unroll
  for (int i = 0; i < 12; ++i) o[i] = 0.f;
  mbar_wait(bars + 16 * AT_ST, 0);
  const uint64_t dq = mk_desc(sq + wg * 4096, 128, 512, 0);
  for (int it = 0; it < SEQ / 128; ++it) {
    const int s = it & 3; const uint32_t ph = (it >> 2) & 1;
    float sc[64];
    mbar_wait(bars + 8 * s, ph);
    const uint64_t dk = mk_desc(skv + s * AT_STAGE, 128, 512, 0);
    wg_fence();
    wgmma_ss_n128_tb0(sc, dq, dk, 0);
    wgmma_ss_n128_tb0(sc, dq + 16, dk + 16, 1);
    wg_commit();
    wg_wait<0>();
    if (it > 0) {
      if (t == 0) mbar_arrive(bars + 8 * (AT_ST + ((it - 1) & 3)));
      if (threadIdx.x == 0 && it >= 2 && it + 2 < SEQ / 128) {
        const int j = it - 2, rs = j & 3;
        mbar_wait(bars + 8 * (AT_ST + rs), (j >> 2) & 1);
        mbar_expect_tx(bars + 8 * rs, AT_STAGE);
        bulk_1d(skv + rs * AT_STAGE, kg + (size_t)(j + 4) * 128 * 32, AT_KB, bars + 8 * rs);
        bulk_1d(skv + rs * AT_STAGE + AT_KB, vg + (size_t)(j + 4) * 128 * 24, AT_VB, bars + 8 * rs);
      }
    }
    float a0 = m0, a1 = m1;
    #pragma unroll
    for (int j = 0; j < 16; ++j) { a0 = fmaxf(a0, fmaxf(sc[4 * j], sc[4 * j + 1])); a1 = fmaxf(a1, fmaxf(sc[4 * j + 2], sc[4 * j + 3])); }
    a0 = fmaxf(a0, __shfl_xor_sync(~0u, a0, 1)); a0 = fmaxf(a0, __shfl_xor_sync(~0u, a0, 2));
    a1 = fmaxf(a1, __shfl_xor_sync(~0u, a1, 1)); a1 = fmaxf(a1, __shfl_xor_sync(~0u, a1, 2));
    const float al0 = ex2((m0 - a0) * cs), al1 = ex2((m1 - a1) * cs);
    m0 = a0; m1 = a1;
    const float b0 = -a0 * cs, b1 = -a1 * cs;
    uint32_t p[32];
    #pragma unroll
    for (int j = 0; j < 16; ++j) {
      p[2 * j] = pack2(ex2(fmaf(sc[4 * j], cs, b0)), ex2(fmaf(sc[4 * j + 1], cs, b0)));
      p[2 * j + 1] = pack2(ex2(fmaf(sc[4 * j + 2], cs, b1)), ex2(fmaf(sc[4 * j + 3], cs, b1)));
    }
    #pragma unroll
    for (int g = 0; g < 3; ++g) { o[4 * g] *= al0; o[4 * g + 1] *= al0; o[4 * g + 2] *= al1; o[4 * g + 3] *= al1; }
    const uint64_t dv = mk_desc(skv + s * AT_STAGE + AT_KB, 384, 128, 0);
    wg_fence();
    #pragma unroll
    for (int j = 0; j < 8; ++j) wgmma_rs_n24_tb1(o, p[4 * j], p[4 * j + 1], p[4 * j + 2], p[4 * j + 3], dv + 48 * j, 1);
    wg_commit();
  }
  wg_wait<0>();
  const float l0 = __shfl_sync(~0u, o[8], (lane & ~3) | 2), l1 = __shfl_sync(~0u, o[10], (lane & ~3) | 2);
  const float i0 = 1.f / l0, i1 = 1.f / l1;
  const int r0 = q0 + wg * 64 + (t >> 5) * 16 + (lane >> 2), cq = 2 * (lane & 3);
  #pragma unroll
  for (int g = 0; g < 3; ++g) {
    if (8 * g + cq < DH) {
      *reinterpret_cast<uint32_t*>(g_attn + (size_t)r0 * DM + hd * DH + 8 * g + cq) = pack2(o[4 * g] * i0, o[4 * g + 1] * i0);
      *reinterpret_cast<uint32_t*>(g_attn + (size_t)(r0 + 8) * DM + hd * DH + 8 * g + cq) = pack2(o[4 * g + 2] * i1, o[4 * g + 3] * i1);
    }
  }
}

typedef CUresult (*EncodeFn)(CUtensorMap*, CUtensorMapDataType, cuuint32_t, void*, const cuuint64_t*, const cuuint64_t*,
                             const cuuint32_t*, const cuuint32_t*, CUtensorMapInterleave, CUtensorMapSwizzle,
                             CUtensorMapL2promotion, CUtensorMapFloatOOBfill);
static void mk_map(EncodeFn enc, CUtensorMap* m, const void* ptr, int cols, int rows, int bc, int br) {
  cuuint64_t dim[2] = {(cuuint64_t)cols, (cuuint64_t)rows}; cuuint64_t str[1] = {(cuuint64_t)cols * 2};
  cuuint32_t box[2] = {(cuuint32_t)bc, (cuuint32_t)br}; cuuint32_t es[2] = {1, 1};
  enc(m, CU_TENSOR_MAP_DATA_TYPE_BFLOAT16, 2, (void*)ptr, dim, str, box, es, CU_TENSOR_MAP_INTERLEAVE_NONE,
      CU_TENSOR_MAP_SWIZZLE_128B, CU_TENSOR_MAP_L2_PROMOTION_L2_256B, CU_TENSOR_MAP_FLOAT_OOB_FILL_NONE);
}
template <int MODE> static constexpr int gemm_smem() { return GCfg<MODE>::ST * (16384 + GCfg<MODE>::NBOX * 8192) + 1024 + 256; }

extern "C" void kernel_launch(void* const* d_in, const int* in_sizes, int n_in, void* d_out, int out_size) {
  static bool init = false;
  static CUtensorMap tLn, tAttn, tAct, tWqkv, tWo, tWg, tWu, tWd;
  static void *pLn, *pH;
  const bf16* x = (const bf16*)d_in[0];
  if (!init) {
    void* fn = nullptr; cudaDriverEntryPointQueryResult qr;
    cudaGetDriverEntryPoint("cuTensorMapEncodeTiled", &fn, cudaEnableDefault, &qr);
    EncodeFn enc = (EncodeFn)fn;
    void *pAttn, *pAct;
    cudaGetSymbolAddress(&pLn, g_ln); cudaGetSymbolAddress(&pAttn, g_attn); cudaGetSymbolAddress(&pAct, g_act); cudaGetSymbolAddress(&pH, g_h);
    mk_map(enc, &tLn, pLn, DM, SEQ, 64, 128);
    mk_map(enc, &tAttn, pAttn, DM, SEQ, 64, 128);
    mk_map(enc, &tAct, pAct, FF, SEQ, 64, 128);
    mk_map(enc, &tWqkv, d_in[1], 3 * DM, DM, 64, 64);
    mk_map(enc, &tWo, d_in[2], DM, DM, 64, 64);
    mk_map(enc, &tWg, d_in[4], FF, DM, 64, 64);
    mk_map(enc, &tWu, d_in[5], FF, DM, 64, 64);
    mk_map(enc, &tWd, d_in[6], DM, FF, 64, 64);
    cudaFuncSetAttribute(gemm_kernel<0>, cudaFuncAttributeMaxDynamicSharedMemorySize, gemm_smem<0>());
    cudaFuncSetAttribute(gemm_kernel<1>, cudaFuncAttributeMaxDynamicSharedMemorySize, gemm_smem<1>());
    cudaFuncSetAttribute(gemm_kernel<2>, cudaFuncAttributeMaxDynamicSharedMemorySize, gemm_smem<2>());
    cudaFuncSetAttribute(gemm_kernel<3>, cudaFuncAttributeMaxDynamicSharedMemorySize, gemm_smem<3>());
    cudaFuncSetAttribute(attn_kernel, cudaFuncAttributeMaxDynamicSharedMemorySize, 16384 + AT_ST * AT_STAGE + 2048);
    init = true;
  }
  cudaStream_t st = cudaStreamPerThread;
  ln_kernel<<<SEQ / 8, 256, 0, st>>>(x, (bf16*)pLn);
  gemm_kernel<0><<<dim3(8, 16), 384, gemm_smem<0>(), st>>>(tLn, tWqkv, tWqkv, nullptr, nullptr);
  attn_kernel<<<dim3(8, 32), 512, 16384 + AT_ST * AT_STAGE + 2048, st>>>();
  gemm_kernel<1><<<dim3(8, 16), 384, gemm_smem<1>(), st>>>(tAttn, tWo, tWo, x, (bf16*)pH);
  ln_kernel<<<SEQ / 8, 256, 0, st>>>((const bf16*)pH, (bf16*)pLn);
  gemm_kernel<2><<<dim3(8, 16), 384, gemm_smem<2>(), st>>>(tLn, tWg, tWu, nullptr, nullptr);
  gemm_kernel<3><<<dim3(8, 16), 384, gemm_smem<3>(), st>>>(tAct, tWd, tWd, (const bf16*)pH, (bf16*)d_out);
}
```

```cpp
#include <cuda_runtime.h>
#include <cuda_bf16.h>
#include <cuda.h>
#include <stdint.h>

typedef __nv_bfloat16 bf16;
constexpr int SEQ = 2048, DM = 640, NH = 32, DH = 20, FF = 1536;

__device__ __align__(1024) bf16 g_ln[SEQ * DM];
__device__ __align__(1024) bf16 g_q[NH * SEQ * 32];
__device__ __align__(1024) bf16 g_k[NH * SEQ * 32];
__device__ __align__(1024) bf16 g_v[NH * SEQ * 24];
__device__ __align__(1024) bf16 g_attn[SEQ * DM];
__device__ __align__(1024) bf16 g_h[SEQ * DM];
__device__ __align__(1024) bf16 g_act[SEQ * FF];

__device__ __forceinline__ uint32_t smem_u32(const void* p) { return (uint32_t)__cvta_generic_to_shared(p); }
__device__ __forceinline__ void mbar_init(uint32_t bar, uint32_t cnt) {
  asm volatile("mbarrier.init.shared::cta.b64 [%0], %1;" :: "r"(bar), "r"(cnt) : "memory");
}
__device__ __forceinline__ void mbar_expect_tx(uint32_t bar, uint32_t bytes) {
  asm volatile("mbarrier.arrive.expect_tx.shared::cta.b64 _, [%0], %1;" :: "r"(bar), "r"(bytes) : "memory");
}
__device__ __forceinline__ void mbar_arrive(uint32_t bar) {
  asm volatile("mbarrier.arrive.shared::cta.b64 _, [%0];" :: "r"(bar) : "memory");
}
__device__ __forceinline__ void mbar_wait(uint32_t bar, uint32_t parity) {
  uint32_t ok;
  #pragma unroll 1
  for (uint32_t it = 0; it < 0x10000000u; ++it) {
    asm volatile("{\n.reg .pred p;\nmbarrier.try_wait.parity.shared::cta.b64 p, [%1], %2;\nselp.u32 %0, 1, 0, p;\n}\n"
                 : "=r"(ok) : "r"(bar), "r"(parity) : "memory");
    if (ok) break;
  }
}
__device__ __forceinline__ void tma_2d(uint32_t dst, const CUtensorMap* tm, int c0, int c1, uint32_t bar) {
  asm volatile("cp.async.bulk.tensor.2d.shared::cluster.global.mbarrier::complete_tx::bytes [%0], [%1, {%3, %4}], [%2];"
               :: "r"(dst), "l"(tm), "r"(bar), "r"(c0), "r"(c1) : "memory");
}
__device__ __forceinline__ void bulk_1d(uint32_t dst, const void* src, uint32_t bytes, uint32_t bar) {
  asm volatile("cp.async.bulk.shared::cluster.global.mbarrier::complete_tx::bytes [%0], [%1], %2, [%3];"
               :: "r"(dst), "l"(src), "r"(bytes), "r"(bar) : "memory");
}
__device__ __forceinline__ void wg_fence() { asm volatile("wgmma.fence.sync.aligned;" ::: "memory"); }
__device__ __forceinline__ void wg_commit() { asm volatile("wgmma.commit_group.sync.aligned;" ::: "memory"); }
template <int N> __device__ __forceinline__ void wg_wait() { asm volatile("wgmma.wait_group.sync.aligned %0;" :: "n"(N) : "memory"); }
__device__ __forceinline__ uint64_t mk_desc(uint32_t addr, uint32_t lbo, uint32_t sbo, uint32_t mode) {
  return (uint64_t)((addr & 0x3FFFF) >> 4) | ((uint64_t)(lbo >> 4) << 16) | ((uint64_t)(sbo >> 4) << 32) | ((uint64_t)mode << 62);
}
__device__ __forceinline__ float bf16r(float x) { return __bfloat162float(__float2bfloat16_rn(x)); }
__device__ __forceinline__ uint32_t pack2(float lo, float hi) {
  __nv_bfloat162 v = __floats2bfloat162_rn(lo, hi);
  return *reinterpret_cast<uint32_t*>(&v);
}
__device__ __forceinline__ float ex2(float x) { float y; asm("ex2.approx.ftz.f32 %0, %1;" : "=f"(y) : "f"(x)); return y; }

__device__ __forceinline__ void wgmma_ss_n240_tb1(float (&d)[120], uint64_t da, uint64_t db, int sd) {
  asm volatile("{\n.reg .pred p;\nsetp.ne.b32 p, %122, 0;\n"
    "wgmma.mma_async.sync.aligned.m64n240k16.f32.bf16.bf16 {%0, %1, %2, %3, %4, %5, %6, %7, %8, %9, %10, %11, %12, %13, %14, %15, %16, %17, %18, %19, %20, %21, %22, %23, %24, %25, %26, %27, %28, %29, %30, %31, %32, %33, %34, %35, %36, %37, %38, %39, %40, %41, %42, %43, %44, %45, %46, %47, %48, %49, %50, %51, %52, %53, %54, %55, %56, %57, %58, %59, %60, %61, %62, %63, %64, %65, %66, %67, %68, %69, %70, %71, %72, %73, %74, %75, %76, %77, %78, %79, %80, %81, %82, %83, %84, %85, %86, %87, %88, %89, %90, %91, %92, %93, %94, %95, %96, %97, %98, %99, %100, %101, %102, %103, %104, %105, %106, %107, %108, %109, %110, %111, %112, %113, %114, %115, %116, %117, %118, %119}, %120, %121, p, 1, 1, 0, 1;\n}\n"
    : "+f"(d[0]), "+f"(d[1]), "+f"(d[2]), "+f"(d[3]), "+f"(d[4]), "+f"(d[5]), "+f"(d[6]), "+f"(d[7]), "+f"(d[8]), "+f"(d[9]), "+f"(d[10]), "+f"(d[11]), "+f"(d[12]), "+f"(d[13]), "+f"(d[14]), "+f"(d[15]), "+f"(d[16]), "+f"(d[17]), "+f"(d[18]), "+f"(d[19]), "+f"(d[20]), "+f"(d[21]), "+f"(d[22]), "+f"(d[23]), "+f"(d[24]), "+f"(d[25]), "+f"(d[26]), "+f"(d[27]), "+f"(d[28]), "+f"(d[29]), "+f"(d[30]), "+f"(d[31]), "+f"(d[32]), "+f"(d[33]), "+f"(d[34]), "+f"(d[35]), "+f"(d[36]), "+f"(d[37]), "+f"(d[38]), "+f"(d[39]), "+f"(d[40]), "+f"(d[41]), "+f"(d[42]), "+f"(d[43]), "+f"(d[44]), "+f"(d[45]), "+f"(d[46]), "+f"(d[47]), "+f"(d[48]), "+f"(d[49]), "+f"(d[50]), "+f"(d[51]), "+f"(d[52]), "+f"(d[53]), "+f"(d[54]), "+f"(d[55]), "+f"(d[56]), "+f"(d[57]), "+f"(d[58]), "+f"(d[59]), "+f"(d[60]), "+f"(d[61]), "+f"(d[62]), "+f"(d[63]), "+f"(d[64]), "+f"(d[65]), "+f"(d[66]), "+f"(d[67]), "+f"(d[68]), "+f"(d[69]), "+f"(d[70]), "+f"(d[71]), "+f"(d[72]), "+f"(d[73]), "+f"(d[74]), "+f"(d[75]), "+f"(d[76]), "+f"(d[77]), "+f"(d[78]), "+f"(d[79]), "+f"(d[80]), "+f"(d[81]), "+f"(d[82]), "+f"(d[83]), "+f"(d[84]), "+f"(d[85]), "+f"(d[86]), "+f"(d[87]), "+f"(d[88]), "+f"(d[89]), "+f"(d[90]), "+f"(d[91]), "+f"(d[92]), "+f"(d[93]), "+f"(d[94]), "+f"(d[95]), "+f"(d[96]), "+f"(d[97]), "+f"(d[98]), "+f"(d[99]), "+f"(d[100]), "+f"(d[101]), "+f"(d[102]), "+f"(d[103]), "+f"(d[104]), "+f"(d[105]), "+f"(d[106]), "+f"(d[107]), "+f"(d[108]), "+f"(d[109]), "+f"(d[110]), "+f"(d[111]), "+f"(d[112]), "+f"(d[113]), "+f"(d[114]), "+f"(d[115]), "+f"(d[116]), "+f"(d[117]), "+f"(d[118]), "+f"(d[119])
    : "l"(da), "l"(db), "r"(sd));
}
__device__ __forceinline__ void wgmma_ss_n80_tb1(float (&d)[40], uint64_t da, uint64_t db, int sd) {
  asm volatile("{\n.reg .pred p;\nsetp.ne.b32 p, %42, 0;\n"
    "wgmma.mma_async.sync.aligned.m64n80k16.f32.bf16.bf16 {%0, %1, %2, %3, %4, %5, %6, %7, %8, %9, %10, %11, %12, %13, %14, %15, %16, %17, %18, %19, %20, %21, %22, %23, %24, %25, %26, %27, %28, %29, %30, %31, %32, %33, %34, %35, %36, %37, %38, %39}, %40, %41, p, 1, 1, 0, 1;\n}\n"
    : "+f"(d[0]), "+f"(d[1]), "+f"(d[2]), "+f"(d[3]), "+f"(d[4]), "+f"(d[5]), "+f"(d[6]), "+f"(d[7]), "+f"(d[8]), "+f"(d[9]), "+f"(d[10]), "+f"(d[11]), "+f"(d[12]), "+f"(d[13]), "+f"(d[14]), "+f"(d[15]), "+f"(d[16]), "+f"(d[17]), "+f"(d[18]), "+f"(d[19]), "+f"(d[20]), "+f"(d[21]), "+f"(d[22]), "+f"(d[23]), "+f"(d[24]), "+f"(d[25]), "+f"(d[26]), "+f"(d[27]), "+f"(d[28]), "+f"(d[29]), "+f"(d[30]), "+f"(d[31]), "+f"(d[32]), "+f"(d[33]), "+f"(d[34]), "+f"(d[35]), "+f"(d[36]), "+f"(d[37]), "+f"(d[38]), "+f"(d[39])
    : "l"(da), "l"(db), "r"(sd));
}
__device__ __forceinline__ void wgmma_ss_n192_tb1(float (&d)[96], uint64_t da, uint64_t db, int sd) {
  asm volatile("{\n.reg .pred p;\nsetp.ne.b32 p, %98, 0;\n"
    "wgmma.mma_async.sync.aligned.m64n192k16.f32.bf16.bf16 {%0, %1, %2, %3, %4, %5, %6, %7, %8, %9, %10, %11, %12, %13, %14, %15, %16, %17, %18, %19, %20, %21, %22, %23, %24, %25, %26, %27, %28, %29, %30, %31, %32, %33, %34, %35, %36, %37, %38, %39, %40, %41, %42, %43, %44, %45, %46, %47, %48, %49, %50, %51, %52, %53, %54, %55, %56, %57, %58, %59, %60, %61, %62, %63, %64, %65, %66, %67, %68, %69, %70, %71, %72, %73, %74, %75, %76, %77, %78, %79, %80, %81, %82, %83, %84, %85, %86, %87, %88, %89, %90, %91, %92, %93, %94, %95}, %96, %97, p, 1, 1, 0, 1;\n}\n"
    : "+f"(d[0]), "+f"(d[1]), "+f"(d[2]), "+f"(d[3]), "+f"(d[4]), "+f"(d[5]), "+f"(d[6]), "+f"(d[7]), "+f"(d[8]), "+f"(d[9]), "+f"(d[10]), "+f"(d[11]), "+f"(d[12]), "+f"(d[13]), "+f"(d[14]), "+f"(d[15]), "+f"(d[16]), "+f"(d[17]), "+f"(d[18]), "+f"(d[19]), "+f"(d[20]), "+f"(d[21]), "+f"(d[22]), "+f"(d[23]), "+f"(d[24]), "+f"(d[25]), "+f"(d[26]), "+f"(d[27]), "+f"(d[28]), "+f"(d[29]), "+f"(d[30]), "+f"(d[31]), "+f"(d[32]), "+f"(d[33]), "+f"(d[34]), "+f"(d[35]), "+f"(d[36]), "+f"(d[37]), "+f"(d[38]), "+f"(d[39]), "+f"(d[40]), "+f"(d[41]), "+f"(d[42]), "+f"(d[43]), "+f"(d[44]), "+f"(d[45]), "+f"(d[46]), "+f"(d[47]), "+f"(d[48]), "+f"(d[49]), "+f"(d[50]), "+f"(d[51]), "+f"(d[52]), "+f"(d[53]), "+f"(d[54]), "+f"(d[55]), "+f"(d[56]), "+f"(d[57]), "+f"(d[58]), "+f"(d[59]), "+f"(d[60]), "+f"(d[61]), "+f"(d[62]), "+f"(d[63]), "+f"(d[64]), "+f"(d[65]), "+f"(d[66]), "+f"(d[67]), "+f"(d[68]), "+f"(d[69]), "+f"(d[70]), "+f"(d[71]), "+f"(d[72]), "+f"(d[73]), "+f"(d[74]), "+f"(d[75]), "+f"(d[76]), "+f"(d[77]), "+f"(d[78]), "+f"(d[79]), "+f"(d[80]), "+f"(d[81]), "+f"(d[82]), "+f"(d[83]), "+f"(d[84]), "+f"(d[85]), "+f"(d[86]), "+f"(d[87]), "+f"(d[88]), "+f"(d[89]), "+f"(d[90]), "+f"(d[91]), "+f"(d[92]), "+f"(d[93]), "+f"(d[94]), "+f"(d[95])
    : "l"(da), "l"(db), "r"(sd));
}
__device__ __forceinline__ void wgmma_ss_n64_tb0(float (&d)[32], uint64_t da, uint64_t db, int sd) {
  asm volatile("{\n.reg .pred p;\nsetp.ne.b32 p, %34, 0;\n"
    "wgmma.mma_async.sync.aligned.m64n64k16.f32.bf16.bf16 {%0, %1, %2, %3, %4, %5, %6, %7, %8, %9, %10, %11, %12, %13, %14, %15, %16, %17, %18, %19, %20, %21, %22, %23, %24, %25, %26, %27, %28, %29, %30, %31}, %32, %33, p, 1, 1, 0, 0;\n}\n"
    : "+f"(d[0]), "+f"(d[1]), "+f"(d[2]), "+f"(d[3]), "+f"(d[4]), "+f"(d[5]), "+f"(d[6]), "+f"(d[7]), "+f"(d[8]), "+f"(d[9]), "+f"(d[10]), "+f"(d[11]), "+f"(d[12]), "+f"(d[13]), "+f"(d[14]), "+f"(d[15]), "+f"(d[16]), "+f"(d[17]), "+f"(d[18]), "+f"(d[19]), "+f"(d[20]), "+f"(d[21]), "+f"(d[22]), "+f"(d[23]), "+f"(d[24]), "+f"(d[25]), "+f"(d[26]), "+f"(d[27]), "+f"(d[28]), "+f"(d[29]), "+f"(d[30]), "+f"(d[31])
    : "l"(da), "l"(db), "r"(sd));
}
__device__ __forceinline__ void wgmma_rs_n24_tb1(float (&d)[12], uint32_t a0, uint32_t a1, uint32_t a2, uint32_t a3, uint64_t db, int sd) {
  asm volatile("{\n.reg .pred p;\nsetp.ne.b32 p, %17, 0;\n"
    "wgmma.mma_async.sync.aligned.m64n24k16.f32.bf16.bf16 {%0, %1, %2, %3, %4, %5, %6, %7, %8, %9, %10, %11}, {%12, %13, %14, %15}, %16, p, 1, 1, 1;\n}\n"
    : "+f"(d[0]), "+f"(d[1]), "+f"(d[2]), "+f"(d[3]), "+f"(d[4]), "+f"(d[5]), "+f"(d[6]), "+f"(d[7]), "+f"(d[8]), "+f"(d[9]), "+f"(d[10]), "+f"(d[11])
    : "r"(a0), "r"(a1), "r"(a2), "r"(a3), "l"(db), "r"(sd));
}


__global__ void __launch_bounds__(256) ln_kernel(const bf16* __restrict__ x, bf16* __restrict__ y) {
  int row = blockIdx.x * 8 + (threadIdx.x >> 5), lane = threadIdx.x & 31;
  const uint4* src = reinterpret_cast<const uint4*>(x + (size_t)row * DM);
  float v[24]; float s = 0.f;
  #pragma unroll
  for (int i = 0; i < 3; ++i) {
    int c = lane + 32 * i;
    uint4 u = make_uint4(0, 0, 0, 0);
    if (c < 80) u = src[c];
    const __nv_bfloat162* p = reinterpret_cast<const __nv_bfloat162*>(&u);
    #pragma unroll
    for (int j = 0; j < 4; ++j) { float2 f = __bfloat1622float2(p[j]); v[i * 8 + 2 * j] = f.x; v[i * 8 + 2 * j + 1] = f.y; s += f.x + f.y; }
  }
  #pragma unroll
  for (int o = 16; o; o >>= 1) s += __shfl_xor_sync(~0u, s, o);
  float mean = s * (1.f / DM), q = 0.f;
  #pragma unroll
  for (int i = 0; i < 3; ++i) if (lane + 32 * i < 80) {
    #pragma unroll
    for (int j = 0; j < 8; ++j) { float d = v[i * 8 + j] - mean; q += d * d; }
  }
  #pragma unroll
  for (int o = 16; o; o >>= 1) q += __shfl_xor_sync(~0u, q, o);
  float mb = bf16r(mean), vb = bf16r(q * (1.f / DM));
  float den = bf16r(sqrtf(bf16r(vb + 1e-5f)));
  uint4* dst = reinterpret_cast<uint4*>(y + (size_t)row * DM);
  #pragma unroll
  for (int i = 0; i < 3; ++i) {
    int c = lane + 32 * i;
    if (c < 80) {
      uint4 u; uint32_t* w = reinterpret_cast<uint32_t*>(&u);
      #pragma unroll
      for (int j = 0; j < 4; ++j) w[j] = pack2(bf16r(v[i * 8 + 2 * j] - mb) / den, bf16r(v[i * 8 + 2 * j + 1] - mb) / den);
      dst[c] = u;
    }
  }
}

template <int MODE> struct GCfg;
template <> struct GCfg<0> { static constexpr int BN = 240, NBOX = 4, ST = 4, KT = 10; };
template <> struct GCfg<1> { static constexpr int BN = 80, NBOX = 2, ST = 6, KT = 10; };
template <> struct GCfg<2> { static constexpr int BN = 192, NBOX = 6, ST = 3, KT = 10; };
template <> struct GCfg<3> { static constexpr int BN = 80, NBOX = 2, ST = 6, KT = 24; };

template <int MODE>
__global__ void __launch_bounds__(384, 1) gemm_kernel(const __grid_constant__ CUtensorMap tmA, const __grid_constant__ CUtensorMap tmB,
                                                      const __grid_constant__ CUtensorMap tmB2, const bf16* __restrict__ resid, bf16* __restrict__ out) {
  using C = GCfg<MODE>;
  constexpr int STAGE = 16384 + C::NBOX * 8192;
  extern __shared__ __align__(1024) uint8_t smem_raw[];
  uint32_t sbase = (smem_u32(smem_raw) + 1023) & ~1023u;
  uint32_t bars = sbase + C::ST * STAGE;
  const int m0 = blockIdx.y * 128, n0 = blockIdx.x * C::BN;
  const int wg = threadIdx.x >> 7;
  if (threadIdx.x == 0) {
    for (int s = 0; s < C::ST; ++s) { mbar_init(bars + 8 * s, 1); mbar_init(bars + 8 * (C::ST + s), 2); }
    asm volatile("fence.mbarrier_init.release.cluster;" ::: "memory");
  }
  __syncthreads();
  if (wg == 0) {
    asm volatile("setmaxnreg.dec.sync.aligned.u32 40;");
    if (threadIdx.x == 0) {
      for (int kt = 0; kt < C::KT; ++kt) {
        int s = kt % C::ST; uint32_t ph = (kt / C::ST) & 1;
        mbar_wait(bars + 8 * (C::ST + s), ph ^ 1);
        uint32_t fb = bars + 8 * s, st = sbase + s * STAGE;
        mbar_expect_tx(fb, STAGE);
        tma_2d(st, &tmA, kt * 64, m0, fb);
        if (MODE == 2) {
          for (int b = 0; b < 3; ++b) tma_2d(st + 16384 + b * 8192, &tmB, n0 + b * 64, kt * 64, fb);
          for (int b = 0; b < 3; ++b) tma_2d(st + 16384 + (3 + b) * 8192, &tmB2, n0 + b * 64, kt * 64, fb);
        } else {
          for (int b = 0; b < C::NBOX; ++b) tma_2d(st + 16384 + b * 8192, &tmB, n0 + b * 64, kt * 64, fb);
        }
      }
    }
  } else {
    asm volatile("setmaxnreg.inc.sync.aligned.u32 232;");
    const int w = wg - 1;
    float acc[C::BN / 2];
    float acc2[MODE == 2 ? 96 : 2];
    for (int kt = 0; kt < C::KT; ++kt) {
      int s = kt % C::ST; uint32_t ph = (kt / C::ST) & 1;
      mbar_wait(bars + 8 * s, ph);
      uint32_t st = sbase + s * STAGE;
      uint64_t da = mk_desc(st + w * 8192, 16, 1024, 1);
      uint64_t db = mk_desc(st + 16384, 8192, 1024, 1);
      wg_fence();
      #pragma unroll
      for (int k = 0; k < 4; ++k) {
        int sd = (kt | k) != 0;
        if constexpr (MODE == 0) wgmma_ss_n240_tb1(acc, da + 2 * k, db + 128 * k, sd);
        else if constexpr (MODE == 2) {
          wgmma_ss_n192_tb1(acc, da + 2 * k, db + 128 * k, sd);
          wgmma_ss_n192_tb1(acc2, da + 2 * k, db + 128 * k + 3 * 512, sd);
        } else wgmma_ss_n80_tb1(acc, da + 2 * k, db + 128 * k, sd);
      }
      wg_commit();
      if (kt > 0) { wg_wait<1>(); if ((threadIdx.x & 127) == 0) mbar_arrive(bars + 8 * (C::ST + (kt - 1) % C::ST)); }
    }
    wg_wait<0>();
    const int t = threadIdx.x & 127, lane = t & 31;
    const int r0 = m0 + w * 64 + (t >> 5) * 16 + (lane >> 2), cq = 2 * (lane & 3);
    if constexpr (MODE == 0) {
      #pragma unroll
      for (int j = 0; j < 30; ++j) {
        int c = n0 + 8 * j + cq; int which = c / DM, cc = c - which * DM, hd = cc / DH, d = cc - hd * DH;
        #pragma unroll
        for (int hh = 0; hh < 2; ++hh) {
          int r = r0 + 8 * hh; uint32_t v = pack2(acc[4 * j + 2 * hh], acc[4 * j + 2 * hh + 1]);
          int inner = (d >> 3) * 64 + (r & 7) * 8 + (d & 7);
          if (which == 2) *reinterpret_cast<uint32_t*>(g_v + (size_t)hd * SEQ * 24 + (r >> 3) * 192 + inner) = v;
          else *reinterpret_cast<uint32_t*>((which ? g_k : g_q) + (size_t)hd * SEQ * 32 + (r >> 3) * 256 + inner) = v;
        }
      }
      for (int i = t; i < 64 * 12; i += 128) {
        int r = m0 + w * 64 + (i & 63); int c = n0 + (i >> 6) * DH; int which = c / DM, hd = (c - which * DM) / DH;
        if (which == 2) *reinterpret_cast<uint2*>(g_v + (size_t)hd * SEQ * 24 + (r >> 3) * 192 + 128 + (r & 7) * 8 + 4) = make_uint2(0x00003F80u, 0u);
        else {
          bf16* p = (which ? g_k : g_q) + (size_t)hd * SEQ * 32 + (r >> 3) * 256 + (r & 7) * 8;
          *reinterpret_cast<uint2*>(p + 128 + 4) = make_uint2(0u, 0u);
          *reinterpret_cast<uint4*>(p + 192) = make_uint4(0u, 0u, 0u, 0u);
        }
      }
    } else if constexpr (MODE == 2) {
      #pragma unroll
      for (int j = 0; j < 24; ++j) {
        #pragma unroll
        for (int hh = 0; hh < 2; ++hh) {
          float o[2];
          #pragma unroll
          for (int e = 0; e < 2; ++e) {
            float g = bf16r(acc[4 * j + 2 * hh + e]), u = bf16r(acc2[4 * j + 2 * hh + e]);
            o[e] = bf16r(g / (1.f + __expf(-g))) * u;
          }
          *reinterpret_cast<uint32_t*>(g_act + (size_t)(r0 + 8 * hh) * FF + n0 + 8 * j + cq) = pack2(o[0], o[1]);
        }
      }
    } else {
      #pragma unroll
      for (int j = 0; j < 10; ++j) {
        #pragma unroll
        for (int hh = 0; hh < 2; ++hh) {
          size_t off = (size_t)(r0 + 8 * hh) * DM + n0 + 8 * j + cq;
          float2 rv = __bfloat1622float2(*reinterpret_cast<const __nv_bfloat162*>(resid + off));
          *reinterpret_cast<uint32_t*>(out + off) = pack2(rv.x + bf16r(acc[4 * j + 2 * hh]), rv.y + bf16r(acc[4 * j + 2 * hh + 1]));
        }
      }
    }
  }
}

constexpr int AT_ST = 4, AT_KB = 8192, AT_VB = 6144, AT_STAGE = AT_KB + AT_VB;
__global__ void __launch_bounds__(512, 1) attn_kernel() {
  extern __shared__ __align__(1024) uint8_t smem_raw[];
  uint32_t sbase = (smem_u32(smem_raw) + 1023) & ~1023u;
  uint32_t sq = sbase, skv = sbase + 16384, bars = skv + AT_ST * AT_STAGE;
  const int hd = blockIdx.y, q0 = blockIdx.x * 256, wg = threadIdx.x >> 7, t = threadIdx.x & 127, lane = t & 31;
  const bf16* kg = g_k + (size_t)hd * SEQ * 32;
  const bf16* vg = g_v + (size_t)hd * SEQ * 24;
  if (threadIdx.x == 0) {
    for (int s = 0; s < AT_ST; ++s) { mbar_init(bars + 8 * s, 1); mbar_init(bars + 8 * (AT_ST + s), 4); }
    mbar_init(bars + 8 * 2 * AT_ST, 1);
    asm volatile("fence.mbarrier_init.release.cluster;" ::: "memory");
    mbar_expect_tx(bars + 16 * AT_ST, 16384);
    bulk_1d(sq, g_q + (size_t)hd * SEQ * 32 + (size_t)q0 * 32, 16384, bars + 16 * AT_ST);
    for (int s = 0; s < AT_ST; ++s) {
      mbar_expect_tx(bars + 8 * s, AT_STAGE);
      bulk_1d(skv + s * AT_STAGE, kg + (size_t)s * 128 * 32, AT_KB, bars + 8 * s);
      bulk_1d(skv + s * AT_STAGE + AT_KB, vg + (size_t)s * 128 * 24, AT_VB, bars + 8 * s);
    }
  }
  __syncthreads();
  const float cs = 0.22360679774997896f * 1.4426950408889634f;
  float o[12]; float m0 = -INFINITY, m1 = -INFINITY, al0, al1;
  #pragma unroll
  for (int i = 0; i < 12; ++i) o[i] = 0.f;
  mbar_wait(bars + 16 * AT_ST, 0);
  const uint64_t dq = mk_desc(sq + wg * 4096, 128, 512, 0);
  float sA[32], sB[32];
#define QK_ISSUE(S, tile) { const int st_ = ((tile) >> 1) & 3; \
    const uint64_t dk_ = mk_desc(skv + st_ * AT_STAGE + ((tile) & 1) * 4096, 128, 512, 0); \
    wg_fence(); wgmma_ss_n64_tb0(S, dq, dk_, 0); wgmma_ss_n64_tb0(S, dq + 16, dk_ + 16, 1); wg_commit(); }
#define ROWMAX(S) { float a0 = m0, a1 = m1; \
    _Pragma("unroll") for (int j = 0; j < 8; ++j) { a0 = fmaxf(a0, fmaxf(S[4 * j], S[4 * j + 1])); a1 = fmaxf(a1, fmaxf(S[4 * j + 2], S[4 * j + 3])); } \
    a0 = fmaxf(a0, __shfl_xor_sync(~0u, a0, 1)); a0 = fmaxf(a0, __shfl_xor_sync(~0u, a0, 2)); \
    a1 = fmaxf(a1, __shfl_xor_sync(~0u, a1, 1)); a1 = fmaxf(a1, __shfl_xor_sync(~0u, a1, 2)); \
    al0 = ex2((m0 - a0) * cs); al1 = ex2((m1 - a1) * cs); m0 = a0; m1 = a1; \
    _Pragma("unroll") for (int g = 0; g < 3; ++g) { o[4 * g] *= al0; o[4 * g + 1] *= al0; o[4 * g + 2] *= al1; o[4 * g + 3] *= al1; } }
#define EXP_PV(S, tile) { const float b0 = -m0 * cs, b1 = -m1 * cs; uint32_t p[16]; \
    _Pragma("unroll") for (int j = 0; j < 8; ++j) { \
      p[2 * j] = pack2(ex2(fmaf(S[4 * j], cs, b0)), ex2(fmaf(S[4 * j + 1], cs, b0))); \
      p[2 * j + 1] = pack2(ex2(fmaf(S[4 * j + 2], cs, b1)), ex2(fmaf(S[4 * j + 3], cs, b1))); } \
    const uint64_t dv_ = mk_desc(skv + (((tile) >> 1) & 3) * AT_STAGE + AT_KB + ((tile) & 1) * 3072, 384, 128, 0); \
    wg_fence(); \
    _Pragma("unroll") for (int j = 0; j < 4; ++j) wgmma_rs_n24_tb1(o, p[4 * j], p[4 * j + 1], p[4 * j + 2], p[4 * j + 3], dv_ + 48 * j, 1); \
    wg_commit(); }
  mbar_wait(bars, 0);
  QK_ISSUE(sA, 0); wg_wait<0>(); ROWMAX(sA);
  for (int it = 0; it < SEQ / 128; ++it) {
    QK_ISSUE(sB, 2 * it + 1);
    if (it > 0) {
      if (t == 0) mbar_arrive(bars + 8 * (AT_ST + ((it - 1) & 3)));
      if (threadIdx.x == 0 && it >= 2 && it + 2 < SEQ / 128) {
        const int j = it - 2, rs = j & 3;
        mbar_wait(bars + 8 * (AT_ST + rs), (j >> 2) & 1);
        mbar_expect_tx(bars + 8 * rs, AT_STAGE);
        bulk_1d(skv + rs * AT_STAGE, kg + (size_t)(j + 4) * 128 * 32, AT_KB, bars + 8 * rs);
        bulk_1d(skv + rs * AT_STAGE + AT_KB, vg + (size_t)(j + 4) * 128 * 24, AT_VB, bars + 8 * rs);
      }
    }
    EXP_PV(sA, 2 * it);
    wg_wait<0>(); ROWMAX(sB);
    const bool more = it + 1 < SEQ / 128;
    if (more) { mbar_wait(bars + 8 * ((it + 1) & 3), ((it + 1) >> 2) & 1); QK_ISSUE(sA, 2 * it + 2); }
    EXP_PV(sB, 2 * it + 1);
    if (more) { wg_wait<0>(); ROWMAX(sA); }
  }
  wg_wait<0>();
  const float l0 = __shfl_sync(~0u, o[8], (lane & ~3) | 2), l1 = __shfl_sync(~0u, o[10], (lane & ~3) | 2);
  const float i0 = 1.f / l0, i1 = 1.f / l1;
  const int r0 = q0 + wg * 64 + (t >> 5) * 16 + (lane >> 2), cq = 2 * (lane & 3);
  #pragma unroll
  for (int g = 0; g < 3; ++g) {
    if (8 * g + cq < DH) {
      *reinterpret_cast<uint32_t*>(g_attn + (size_t)r0 * DM + hd * DH + 8 * g + cq) = pack2(o[4 * g] * i0, o[4 * g + 1] * i0);
      *reinterpret_cast<uint32_t*>(g_attn + (size_t)(r0 + 8) * DM + hd * DH + 8 * g + cq) = pack2(o[4 * g + 2] * i1, o[4 * g + 3] * i1);
    }
  }
}

typedef CUresult (*EncodeFn)(CUtensorMap*, CUtensorMapDataType, cuuint32_t, void*, const cuuint64_t*, const cuuint64_t*,
                             const cuuint32_t*, const cuuint32_t*, CUtensorMapInterleave, CUtensorMapSwizzle,
                             CUtensorMapL2promotion, CUtensorMapFloatOOBfill);
static void mk_map(EncodeFn enc, CUtensorMap* m, const void* ptr, int cols, int rows, int bc, int br) {
  cuuint64_t dim[2] = {(cuuint64_t)cols, (cuuint64_t)rows}; cuuint64_t str[1] = {(cuuint64_t)cols * 2};
  cuuint32_t box[2] = {(cuuint32_t)bc, (cuuint32_t)br}; cuuint32_t es[2] = {1, 1};
  enc(m, CU_TENSOR_MAP_DATA_TYPE_BFLOAT16, 2, (void*)ptr, dim, str, box, es, CU_TENSOR_MAP_INTERLEAVE_NONE,
      CU_TENSOR_MAP_SWIZZLE_128B, CU_TENSOR_MAP_L2_PROMOTION_L2_256B, CU_TENSOR_MAP_FLOAT_OOB_FILL_NONE);
}
template <int MODE> static constexpr int gemm_smem() { return GCfg<MODE>::ST * (16384 + GCfg<MODE>::NBOX * 8192) + 1024 + 256; }

extern "C" void kernel_launch(void* const* d_in, const int* in_sizes, int n_in, void* d_out, int out_size) {
  static bool init = false;
  static CUtensorMap tLn, tAttn, tAct, tWqkv, tWo, tWg, tWu, tWd;
  static void *pLn, *pH;
  const bf16* x = (const bf16*)d_in[0];
  if (!init) {
    void* fn = nullptr; cudaDriverEntryPointQueryResult qr;
    cudaGetDriverEntryPoint("cuTensorMapEncodeTiled", &fn, cudaEnableDefault, &qr);
    EncodeFn enc = (EncodeFn)fn;
    void *pAttn, *pAct;
    cudaGetSymbolAddress(&pLn, g_ln); cudaGetSymbolAddress(&pAttn, g_attn); cudaGetSymbolAddress(&pAct, g_act); cudaGetSymbolAddress(&pH, g_h);
    mk_map(enc, &tLn, pLn, DM, SEQ, 64, 128);
    mk_map(enc, &tAttn, pAttn, DM, SEQ, 64, 128);
    mk_map(enc, &tAct, pAct, FF, SEQ, 64, 128);
    mk_map(enc, &tWqkv, d_in[1], 3 * DM, DM, 64, 64);
    mk_map(enc, &tWo, d_in[2], DM, DM, 64, 64);
    mk_map(enc, &tWg, d_in[4], FF, DM, 64, 64);
    mk_map(enc, &tWu, d_in[5], FF, DM, 64, 64);
    mk_map(enc, &tWd, d_in[6], DM, FF, 64, 64);
    cudaFuncSetAttribute(gemm_kernel<0>, cudaFuncAttributeMaxDynamicSharedMemorySize, gemm_smem<0>());
    cudaFuncSetAttribute(gemm_kernel<1>, cudaFuncAttributeMaxDynamicSharedMemorySize, gemm_smem<1>());
    cudaFuncSetAttribute(gemm_kernel<2>, cudaFuncAttributeMaxDynamicSharedMemorySize, gemm_smem<2>());
    cudaFuncSetAttribute(gemm_kernel<3>, cudaFuncAttributeMaxDynamicSharedMemorySize, gemm_smem<3>());
    cudaFuncSetAttribute(attn_kernel, cudaFuncAttributeMaxDynamicSharedMemorySize, 16384 + AT_ST * AT_STAGE + 2048);
    init = true;
  }
  cudaStream_t st = cudaStreamPerThread;
  ln_kernel<<<SEQ / 8, 256, 0, st>>>(x, (bf16*)pLn);
  gemm_kernel<0><<<dim3(8, 16), 384, gemm_smem<0>(), st>>>(tLn, tWqkv, tWqkv, nullptr, nullptr);
  attn_kernel<<<dim3(8, 32), 512, 16384 + AT_ST * AT_STAGE + 2048, st>>>();
  gemm_kernel<1><<<dim3(8, 16), 384, gemm_smem<1>(), st>>>(tAttn, tWo, tWo, x, (bf16*)pH);
  ln_kernel<<<SEQ / 8, 256, 0, st>>>((const bf16*)pH, (bf16*)pLn);
  gemm_kernel<2><<<dim3(8, 16), 384, gemm_smem<2>(), st>>>(tLn, tWg, tWu, nullptr, nullptr);
  gemm_kernel<3><<<dim3(8, 16), 384, gemm_smem<3>(), st>>>(tAct, tWd, tWd, (const bf16*)pH, (bf16*)d_out);
}
```
